```python
import torch

def _softmax(x, axis=-1):
    return torch.softmax(x, dim=axis)
def _gelu(x):
    return torch.nn.functional.gelu(x, approximate="tanh")
def _silu(x):
    return torch.nn.functional.silu(x)
def _sigmoid(x):
    return torch.sigmoid(x)
def _layernorm(x, axis=-1, eps=1e-5):
    m = x.mean(dim=axis, keepdim=True)
    v = x.var(dim=axis, keepdim=True, unbiased=False)
    return (x - m) / torch.sqrt(v + eps)
def _scatter_add(tgt, idx, src, axis=0):
    return tgt.clone().index_add_(axis, idx, src)
def _segment_sum(src, seg, n):
    out = torch.zeros((n,) + src.shape[1:], dtype=src.dtype)
    return out.index_add_(0, seg, src)
def _pad(x, pw):
    flat = tuple(v for pair in reversed(pw) for v in pair)
    return torch.nn.functional.pad(x, flat)

kernel_name = 'gated_mix__softmax_full_mha__dense_activation_squared_relu__prompt'

def setup_inputs():

    _w = (lambda a: (lambda t: t.to(torch.bfloat16) if t.is_floating_point() else t)(torch.as_tensor(a)))
    def _A_setup():
        B, S, D = 1, 2048, 640
        return {
            "x": _w((lambda *s: torch.randn(*s, dtype=torch.bfloat16) * 0.05)(B, S, D)),
            "wqkv": _w((lambda *s: torch.randn(*s, dtype=torch.bfloat16) * 0.8)(D, 3 * D)),
            "wo": _w((lambda *s: torch.randn(*s, dtype=torch.bfloat16) * 0.1)(D, D)),
        }
    _A_in = _A_setup()

    def _B_setup():
        B, S, D, F = 1, 2048, 640, 1536
        return {
            "x": _w((lambda *s: torch.randn(*s, dtype=torch.bfloat16) * 0.05)(B, S, D)),
            "w1": _w((lambda *s: torch.randn(*s, dtype=torch.bfloat16) * 0.1)(D, F)),
            "b1": _w((lambda *s: torch.randn(*s, dtype=torch.bfloat16) * 0.1)(F)),
            "w2": _w((lambda *s: torch.randn(*s, dtype=torch.bfloat16) * 0.1)(F, D)),
            "b2": _w((lambda *s: torch.randn(*s, dtype=torch.bfloat16) * 0.05)(D)),
        }
    _B_in = _B_setup()

    return {
        "A_x": _A_in["x"],
        "A_wqkv": _A_in["wqkv"],
        "A_wo": _A_in["wo"],
        "B_x": _B_in["x"],
        "B_w1": _B_in["w1"],
        "B_b1": _B_in["b1"],
        "B_w2": _B_in["w2"],
        "B_b2": _B_in["b2"],
        "gate_w": _w((lambda *s: torch.randn(*s, dtype=torch.bfloat16) * 0.05)(640) * 16.0),
    }

def reference(A_x, A_wqkv, A_wo, B_x, B_w1, B_b1, B_w2, B_b2, gate_w):
    def _A_ref(x, wqkv, wo):
        B, S, D = x.shape
        H = 32; Dh = D // H
        qkv = (lambda x, *d: x.permute(*d))((x @ wqkv).reshape(B, S, 3, H, Dh), 2, 0, 3, 1, 4)
        q, k, v = qkv[0], qkv[1], qkv[2]
        scale = Dh ** -0.5
        scores = torch.einsum("bhqd,bhkd->bhqk", q, k) * scale
        p = _softmax(scores, axis=-1)
        o = torch.einsum("bhqk,bhkd->bhqd", p, v)
        return (lambda x, *d: x.permute(*d))(o, 0, 2, 1, 3).reshape(B, S, D) @ wo

    def _B_ref(x, w1, b1, w2, b2):
        h = torch.einsum("bsd,df->bsf", x, w1) + b1
        zero = torch.zeros_like(h)
        r = torch.where(h > zero, h, zero)
        h = r * r
        out = torch.einsum("bsf,fd->bsd", h, w2) + b2
        return out

    x = A_x
    g = _sigmoid((x * gate_w).sum(-1, keepdims=True))
    a = _A_ref(x, A_wqkv, A_wo)
    b = _B_ref(x, B_w1, B_b1, B_w2, B_b2)
    return g * a + (1 - g) * b
```

```cpp
#include <cuda_runtime.h>
#include <cuda_bf16.h>
#include <cuda.h>
#include <stdint.h>

namespace {

constexpr uint32_t POLYMASK = 0xF0F0;

constexpr int FILLER = 15;

__device__ __align__(1024) uint8_t g_Q[32 * 98304];
__device__ __align__(1024) uint8_t g_KV[32 * 196608];
__device__ __align__(1024) __nv_bfloat16 g_H[2048 * 1536];
__device__ __align__(1024) __nv_bfloat16 g_O[2048 * 640];
__device__ __align__(16) float g_gate[2048];
__device__ __align__(16) float g_nrm[96 * 128];
enum { C_QKV = 0, C_G = 16, C_H = 17, C_O = 33, C_DONE = 65, C_NUM = 66 };
__device__ uint32_t g_cnt[C_NUM * 32];

constexpr uint32_t SB = 1024;
constexpr uint32_t SM_X = SB;
constexpr uint32_t SM_W = SB + 163840;
constexpr uint32_t SM_STG = SM_W + 49152;
constexpr uint32_t SM_Q = SB;
constexpr uint32_t SM_KV = SB + 12288;
constexpr uint32_t SM_G = SB + 81920;
constexpr uint32_t SM_WO = SB + 73728;
constexpr uint32_t SM_OA = SB + 196608;
constexpr uint32_t SM_BAR = SB + 229376;
enum { B_EW = 0,
       B_KE = 20, B_AD = 52, B_OD = 53,
       B_FX = 60, B_FW = 70, B_KF = 90, B_F1 = 122, B_F2 = 142, B_WF = 166, B_OA = 176, B_OB = 186, B_XF = 196, B_EP = 200, B_OF = 201, B_RX = 202, B_NUM = 211 };
constexpr uint32_t SM_EPOCH = SM_BAR + 8 * B_NUM;
constexpr uint32_t SM_ORD = SM_EPOCH + 16;
constexpr uint32_t SM_FAST = SM_EPOCH + 4;
constexpr uint32_t SM_BYTES = SM_ORD + 48 - SB;
__device__ __forceinline__ constexpr uint32_t BAR(int i) { return SM_BAR + 8 * i; }

__device__ __forceinline__ void wg_fence() { asm volatile("wgmma.fence.sync.aligned;" ::: "memory"); }
__device__ __forceinline__ void wg_commit() { asm volatile("wgmma.commit_group.sync.aligned;" ::: "memory"); }
template <int N> __device__ __forceinline__ void wg_wait() { asm volatile("wgmma.wait_group.sync.aligned %0;" ::"n"(N) : "memory"); }
template <int N> __device__ __forceinline__ void pin(float (&d)[N]) {
#pragma unroll
  for (int i = 0; i < N; i++) asm volatile("" : "+f"(d[i])::"memory");
}
template <int N> __device__ __forceinline__ void pin(uint32_t (&d)[N]) {
#pragma unroll
  for (int i = 0; i < N; i++) asm volatile("" : "+r"(d[i])::"memory");
}
__device__ __forceinline__ void mbar_expect(uint32_t a, uint32_t bytes) {
  asm volatile("mbarrier.arrive.expect_tx.shared::cta.b64 _, [%0], %1;" ::"r"(a), "r"(bytes) : "memory");
}
__device__ __forceinline__ void mbar_arrive_lane0(uint32_t a) {
  asm volatile("{.reg .pred p; elect.sync _|p, 0xffffffff; @p mbarrier.arrive.shared::cta.b64 _, [%0];}" ::"r"(a) : "memory");
}
__device__ __forceinline__ void mbar_wait(uint32_t a) {
  asm volatile(
      "{.reg .pred p; .reg .u32 n;\n"
      "mbarrier.try_wait.parity.shared::cta.b64 p, [%0], 0;\n"
      "@p bra DONE;\n"
      "mov.u32 n, 0;\n"
      "LOOP:\n"
      "mbarrier.try_wait.parity.shared::cta.b64 p, [%0], 0;\n"
      "@p bra DONE;\n"
      "add.u32 n, n, 1;\n"
      "setp.lt.u32 p, n, 400000;\n"
      "@p bra LOOP;\n"
      "DONE:\n}" ::"r"(a) : "memory");
}
__device__ __forceinline__ bool mbar_test(uint32_t a) {
  uint32_t r;
  asm volatile("{.reg .pred p; mbarrier.test_wait.parity.shared::cta.b64 p, [%1], 0; selp.u32 %0, 1, 0, p;}" : "=r"(r) : "r"(a) : "memory");
  return r;
}
__device__ __forceinline__ void mbar_wait_slow(uint32_t a) {
  asm volatile(
      "{.reg .pred p; .reg .u32 n;\n"
      "mov.u32 n, 0;\n"
      "LOOP:\n"
      "mbarrier.test_wait.parity.shared::cta.b64 p, [%0], 0;\n"
      "@p bra DONE;\n"
      "nanosleep.u32 100;\n"
      "add.u32 n, n, 1;\n"
      "setp.lt.u32 p, n, 2000000;\n"
      "@p bra LOOP;\n"
      "DONE:\n}" ::"r"(a) : "memory");
}
__device__ __forceinline__ bool elect_one() {
  uint32_t p;
  asm volatile("{.reg .pred P; elect.sync _|P, 0xffffffff; selp.u32 %0, 1, 0, P;}" : "=r"(p));
  return p;
}
__device__ __forceinline__ void bar_wg(int id) { asm volatile("bar.sync %0, 128;" ::"r"(id) : "memory"); }
__device__ __forceinline__ void bar_wg4() { asm volatile("bar.sync 5, 128;" ::: "memory"); }
__device__ __forceinline__ void flag_add(int idx) {
  asm volatile("red.release.gpu.global.add.u32 [%0], 1;" ::"l"(&g_cnt[idx * 32]) : "memory");
}
__device__ __forceinline__ void flag_wait(int idx, uint32_t target) {
  for (int n = 0; n < 2000000; n++) {
    uint32_t v;
    asm volatile("ld.relaxed.gpu.global.u32 %0, [%1];" : "=r"(v) : "l"(&g_cnt[idx * 32]) : "memory");
    if ((int32_t)(v - target) >= 0) break;
  }
}
__device__ __forceinline__ void fence_acquire() { asm volatile("fence.acquire.gpu;" ::: "memory"); }
__device__ __forceinline__ void fence_async_g() { asm volatile("fence.proxy.async.global;" ::: "memory"); }
__device__ __forceinline__ void fence_async_s() { asm volatile("fence.proxy.async.shared::cta;" ::: "memory"); }
__device__ __forceinline__ void tma2d(uint32_t dst, const CUtensorMap* tm, int c0, int c1, uint32_t bar) {
  asm volatile("cp.async.bulk.tensor.2d.shared::cluster.global.mbarrier::complete_tx::bytes [%0], [%1, {%3, %4}], [%2];"
               ::"r"(dst), "l"(tm), "r"(bar), "r"(c0), "r"(c1) : "memory");
}
__device__ __forceinline__ void tma2d_store(const CUtensorMap* tm, int c0, int c1, uint32_t src) {
  asm volatile("cp.async.bulk.tensor.2d.global.shared::cta.bulk_group [%0, {%2, %3}], [%1];"
               ::"l"(tm), "r"(src), "r"(c0), "r"(c1) : "memory");
}
__device__ __forceinline__ void bulk_load(uint32_t dst, const void* src, uint32_t bytes, uint32_t bar) {
  asm volatile("cp.async.bulk.shared::cluster.global.mbarrier::complete_tx::bytes [%0], [%1], %2, [%3];"
               ::"r"(dst), "l"(src), "r"(bytes), "r"(bar) : "memory");
}
__device__ __forceinline__ void l2_prefetch(const void* src, uint32_t bytes) {
  asm volatile("cp.async.bulk.prefetch.L2.global [%0], %1;" ::"l"(src), "r"(bytes) : "memory");
}
__device__ __forceinline__ float ex2(float x) { float y; asm("ex2.approx.ftz.f32 %0, %1;" : "=f"(y) : "f"(x)); return y; }
__device__ __forceinline__ uint32_t pack_bf16(float lo, float hi) {
  uint32_t r; asm("cvt.rn.bf16x2.f32 %0, %1, %2;" : "=r"(r) : "f"(hi), "f"(lo)); return r;
}
__device__ __forceinline__ float bf_lo(uint32_t v) { return __uint_as_float(v << 16); }
__device__ __forceinline__ float bf_hi(uint32_t v) { return __uint_as_float(v & 0xffff0000u); }
constexpr uint64_t mkdesc(uint32_t lbo, uint32_t sbo, uint32_t sw) {
  return ((uint64_t)(lbo >> 4) << 16) | ((uint64_t)(sbo >> 4) << 32) | ((uint64_t)sw << 62);
}
constexpr uint64_t DESC_A128 = mkdesc(16, 1024, 1);
constexpr uint64_t DESC_B128 = mkdesc(8192, 1024, 1);
constexpr uint64_t DESC_B64 = mkdesc(4096, 512, 2);
constexpr uint64_t DESC_C = mkdesc(128, 256, 0);
constexpr uint64_t NO_LBO = (uint64_t)(8u << 16);

__device__ __forceinline__ void mma_ss64_set(float (&d)[32], uint64_t da, uint64_t db) {
  asm volatile("{.reg .pred p; setp.ne.b32 p, 0, 0;\n"
      "wgmma.mma_async.sync.aligned.m64n64k16.f32.bf16.bf16 {"
      "%0, %1, %2, %3, %4, %5, %6, %7, %8, %9, %10, %11, %12, %13, %14, %15, "
      "%16, %17, %18, %19, %20, %21, %22, %23, %24, %25, %26, %27, %28, %29, %30, %31}, %32, %33, p, 1, 1, 0, 0;}\n"
      : "=f"(d[0]), "=f"(d[1]), "=f"(d[2]), "=f"(d[3]), "=f"(d[4]), "=f"(d[5]), "=f"(d[6]), "=f"(d[7]),
        "=f"(d[8]), "=f"(d[9]), "=f"(d[10]), "=f"(d[11]), "=f"(d[12]), "=f"(d[13]), "=f"(d[14]), "=f"(d[15]),
        "=f"(d[16]), "=f"(d[17]), "=f"(d[18]), "=f"(d[19]), "=f"(d[20]), "=f"(d[21]), "=f"(d[22]), "=f"(d[23]),
        "=f"(d[24]), "=f"(d[25]), "=f"(d[26]), "=f"(d[27]), "=f"(d[28]), "=f"(d[29]), "=f"(d[30]), "=f"(d[31])
      : "l"(da), "l"(db));
}
__device__ __forceinline__ void mma_ss64_acc(float (&d)[32], uint64_t da, uint64_t db) {
  asm volatile("{.reg .pred p; setp.ne.b32 p, 1, 0;\n"
      "wgmma.mma_async.sync.aligned.m64n64k16.f32.bf16.bf16 {"
      "%0, %1, %2, %3, %4, %5, %6, %7, %8, %9, %10, %11, %12, %13, %14, %15, "
      "%16, %17, %18, %19, %20, %21, %22, %23, %24, %25, %26, %27, %28, %29, %30, %31}, %32, %33, p, 1, 1, 0, 0;}\n"
      : "+f"(d[0]), "+f"(d[1]), "+f"(d[2]), "+f"(d[3]), "+f"(d[4]), "+f"(d[5]), "+f"(d[6]), "+f"(d[7]),
        "+f"(d[8]), "+f"(d[9]), "+f"(d[10]), "+f"(d[11]), "+f"(d[12]), "+f"(d[13]), "+f"(d[14]), "+f"(d[15]),
        "+f"(d[16]), "+f"(d[17]), "+f"(d[18]), "+f"(d[19]), "+f"(d[20]), "+f"(d[21]), "+f"(d[22]), "+f"(d[23]),
        "+f"(d[24]), "+f"(d[25]), "+f"(d[26]), "+f"(d[27]), "+f"(d[28]), "+f"(d[29]), "+f"(d[30]), "+f"(d[31])
      : "l"(da), "l"(db));
}
__device__ __forceinline__ void mma_st80_sel(float (&d)[40], uint64_t da, uint64_t db, int sd) {
  asm volatile("{.reg .pred p; setp.ne.b32 p, %42, 0;\n"
      "wgmma.mma_async.sync.aligned.m64n80k16.f32.bf16.bf16 {"
      "%0, %1, %2, %3, %4, %5, %6, %7, %8, %9, %10, %11, %12, %13, %14, %15, "
      "%16, %17, %18, %19, %20, %21, %22, %23, %24, %25, %26, %27, %28, %29, %30, %31, "
      "%32, %33, %34, %35, %36, %37, %38, %39}, %40, %41, p, 1, 1, 0, 1;}\n"
      : "+f"(d[0]), "+f"(d[1]), "+f"(d[2]), "+f"(d[3]), "+f"(d[4]), "+f"(d[5]), "+f"(d[6]), "+f"(d[7]),
        "+f"(d[8]), "+f"(d[9]), "+f"(d[10]), "+f"(d[11]), "+f"(d[12]), "+f"(d[13]), "+f"(d[14]), "+f"(d[15]),
        "+f"(d[16]), "+f"(d[17]), "+f"(d[18]), "+f"(d[19]), "+f"(d[20]), "+f"(d[21]), "+f"(d[22]), "+f"(d[23]),
        "+f"(d[24]), "+f"(d[25]), "+f"(d[26]), "+f"(d[27]), "+f"(d[28]), "+f"(d[29]), "+f"(d[30]), "+f"(d[31]),
        "+f"(d[32]), "+f"(d[33]), "+f"(d[34]), "+f"(d[35]), "+f"(d[36]), "+f"(d[37]), "+f"(d[38]), "+f"(d[39])
      : "l"(da), "l"(db), "r"(sd));
}
__device__ __forceinline__ void mma_st80_acc(float (&d)[40], uint64_t da, uint64_t db) {
  asm volatile("{.reg .pred p; setp.ne.b32 p, 1, 0;\n"
      "wgmma.mma_async.sync.aligned.m64n80k16.f32.bf16.bf16 {"
      "%0, %1, %2, %3, %4, %5, %6, %7, %8, %9, %10, %11, %12, %13, %14, %15, "
      "%16, %17, %18, %19, %20, %21, %22, %23, %24, %25, %26, %27, %28, %29, %30, %31, "
      "%32, %33, %34, %35, %36, %37, %38, %39}, %40, %41, p, 1, 1, 0, 1;}\n"
      : "+f"(d[0]), "+f"(d[1]), "+f"(d[2]), "+f"(d[3]), "+f"(d[4]), "+f"(d[5]), "+f"(d[6]), "+f"(d[7]),
        "+f"(d[8]), "+f"(d[9]), "+f"(d[10]), "+f"(d[11]), "+f"(d[12]), "+f"(d[13]), "+f"(d[14]), "+f"(d[15]),
        "+f"(d[16]), "+f"(d[17]), "+f"(d[18]), "+f"(d[19]), "+f"(d[20]), "+f"(d[21]), "+f"(d[22]), "+f"(d[23]),
        "+f"(d[24]), "+f"(d[25]), "+f"(d[26]), "+f"(d[27]), "+f"(d[28]), "+f"(d[29]), "+f"(d[30]), "+f"(d[31]),
        "+f"(d[32]), "+f"(d[33]), "+f"(d[34]), "+f"(d[35]), "+f"(d[36]), "+f"(d[37]), "+f"(d[38]), "+f"(d[39])
      : "l"(da), "l"(db));
}
__device__ __forceinline__ void mma_st96_sel(float (&d)[48], uint64_t da, uint64_t db, int sd) {
  asm volatile("{.reg .pred p; setp.ne.b32 p, %50, 0;\n"
      "wgmma.mma_async.sync.aligned.m64n96k16.f32.bf16.bf16 {"
      "%0, %1, %2, %3, %4, %5, %6, %7, %8, %9, %10, %11, %12, %13, %14, %15, "
      "%16, %17, %18, %19, %20, %21, %22, %23, %24, %25, %26, %27, %28, %29, %30, %31, "
      "%32, %33, %34, %35, %36, %37, %38, %39, %40, %41, %42, %43, %44, %45, %46, %47}, %48, %49, p, 1, 1, 0, 1;}\n"
      : "+f"(d[0]), "+f"(d[1]), "+f"(d[2]), "+f"(d[3]), "+f"(d[4]), "+f"(d[5]), "+f"(d[6]), "+f"(d[7]),
        "+f"(d[8]), "+f"(d[9]), "+f"(d[10]), "+f"(d[11]), "+f"(d[12]), "+f"(d[13]), "+f"(d[14]), "+f"(d[15]),
        "+f"(d[16]), "+f"(d[17]), "+f"(d[18]), "+f"(d[19]), "+f"(d[20]), "+f"(d[21]), "+f"(d[22]), "+f"(d[23]),
        "+f"(d[24]), "+f"(d[25]), "+f"(d[26]), "+f"(d[27]), "+f"(d[28]), "+f"(d[29]), "+f"(d[30]), "+f"(d[31]),
        "+f"(d[32]), "+f"(d[33]), "+f"(d[34]), "+f"(d[35]), "+f"(d[36]), "+f"(d[37]), "+f"(d[38]), "+f"(d[39]),
        "+f"(d[40]), "+f"(d[41]), "+f"(d[42]), "+f"(d[43]), "+f"(d[44]), "+f"(d[45]), "+f"(d[46]), "+f"(d[47])
      : "l"(da), "l"(db), "r"(sd));
}
__device__ __forceinline__ void mma_st96_acc(float (&d)[48], uint64_t da, uint64_t db) {
  asm volatile("{.reg .pred p; setp.ne.b32 p, 1, 0;\n"
      "wgmma.mma_async.sync.aligned.m64n96k16.f32.bf16.bf16 {"
      "%0, %1, %2, %3, %4, %5, %6, %7, %8, %9, %10, %11, %12, %13, %14, %15, "
      "%16, %17, %18, %19, %20, %21, %22, %23, %24, %25, %26, %27, %28, %29, %30, %31, "
      "%32, %33, %34, %35, %36, %37, %38, %39, %40, %41, %42, %43, %44, %45, %46, %47}, %48, %49, p, 1, 1, 0, 1;}\n"
      : "+f"(d[0]), "+f"(d[1]), "+f"(d[2]), "+f"(d[3]), "+f"(d[4]), "+f"(d[5]), "+f"(d[6]), "+f"(d[7]),
        "+f"(d[8]), "+f"(d[9]), "+f"(d[10]), "+f"(d[11]), "+f"(d[12]), "+f"(d[13]), "+f"(d[14]), "+f"(d[15]),
        "+f"(d[16]), "+f"(d[17]), "+f"(d[18]), "+f"(d[19]), "+f"(d[20]), "+f"(d[21]), "+f"(d[22]), "+f"(d[23]),
        "+f"(d[24]), "+f"(d[25]), "+f"(d[26]), "+f"(d[27]), "+f"(d[28]), "+f"(d[29]), "+f"(d[30]), "+f"(d[31]),
        "+f"(d[32]), "+f"(d[33]), "+f"(d[34]), "+f"(d[35]), "+f"(d[36]), "+f"(d[37]), "+f"(d[38]), "+f"(d[39]),
        "+f"(d[40]), "+f"(d[41]), "+f"(d[42]), "+f"(d[43]), "+f"(d[44]), "+f"(d[45]), "+f"(d[46]), "+f"(d[47])
      : "l"(da), "l"(db));
}
__device__ __forceinline__ void mma_st128_sel(float (&d)[64], uint64_t da, uint64_t db, int sd) {
  asm volatile("{.reg .pred p; setp.ne.b32 p, %66, 0;\n"
      "wgmma.mma_async.sync.aligned.m64n128k16.f32.bf16.bf16 {"
      "%0, %1, %2, %3, %4, %5, %6, %7, %8, %9, %10, %11, %12, %13, %14, %15, "
      "%16, %17, %18, %19, %20, %21, %22, %23, %24, %25, %26, %27, %28, %29, %30, %31, "
      "%32, %33, %34, %35, %36, %37, %38, %39, %40, %41, %42, %43, %44, %45, %46, %47, "
      "%48, %49, %50, %51, %52, %53, %54, %55, %56, %57, %58, %59, %60, %61, %62, %63}, %64, %65, p, 1, 1, 0, 1;}\n"
      : "+f"(d[0]), "+f"(d[1]), "+f"(d[2]), "+f"(d[3]), "+f"(d[4]), "+f"(d[5]), "+f"(d[6]), "+f"(d[7]),
        "+f"(d[8]), "+f"(d[9]), "+f"(d[10]), "+f"(d[11]), "+f"(d[12]), "+f"(d[13]), "+f"(d[14]), "+f"(d[15]),
        "+f"(d[16]), "+f"(d[17]), "+f"(d[18]), "+f"(d[19]), "+f"(d[20]), "+f"(d[21]), "+f"(d[22]), "+f"(d[23]),
        "+f"(d[24]), "+f"(d[25]), "+f"(d[26]), "+f"(d[27]), "+f"(d[28]), "+f"(d[29]), "+f"(d[30]), "+f"(d[31]),
        "+f"(d[32]), "+f"(d[33]), "+f"(d[34]), "+f"(d[35]), "+f"(d[36]), "+f"(d[37]), "+f"(d[38]), "+f"(d[39]),
        "+f"(d[40]), "+f"(d[41]), "+f"(d[42]), "+f"(d[43]), "+f"(d[44]), "+f"(d[45]), "+f"(d[46]), "+f"(d[47]),
        "+f"(d[48]), "+f"(d[49]), "+f"(d[50]), "+f"(d[51]), "+f"(d[52]), "+f"(d[53]), "+f"(d[54]), "+f"(d[55]),
        "+f"(d[56]), "+f"(d[57]), "+f"(d[58]), "+f"(d[59]), "+f"(d[60]), "+f"(d[61]), "+f"(d[62]), "+f"(d[63])
      : "l"(da), "l"(db), "r"(sd));
}
__device__ __forceinline__ void mma_st128_acc(float (&d)[64], uint64_t da, uint64_t db) {
  asm volatile("{.reg .pred p; setp.ne.b32 p, 1, 0;\n"
      "wgmma.mma_async.sync.aligned.m64n128k16.f32.bf16.bf16 {"
      "%0, %1, %2, %3, %4, %5, %6, %7, %8, %9, %10, %11, %12, %13, %14, %15, "
      "%16, %17, %18, %19, %20, %21, %22, %23, %24, %25, %26, %27, %28, %29, %30, %31, "
      "%32, %33, %34, %35, %36, %37, %38, %39, %40, %41, %42, %43, %44, %45, %46, %47, "
      "%48, %49, %50, %51, %52, %53, %54, %55, %56, %57, %58, %59, %60, %61, %62, %63}, %64, %65, p, 1, 1, 0, 1;}\n"
      : "+f"(d[0]), "+f"(d[1]), "+f"(d[2]), "+f"(d[3]), "+f"(d[4]), "+f"(d[5]), "+f"(d[6]), "+f"(d[7]),
        "+f"(d[8]), "+f"(d[9]), "+f"(d[10]), "+f"(d[11]), "+f"(d[12]), "+f"(d[13]), "+f"(d[14]), "+f"(d[15]),
        "+f"(d[16]), "+f"(d[17]), "+f"(d[18]), "+f"(d[19]), "+f"(d[20]), "+f"(d[21]), "+f"(d[22]), "+f"(d[23]),
        "+f"(d[24]), "+f"(d[25]), "+f"(d[26]), "+f"(d[27]), "+f"(d[28]), "+f"(d[29]), "+f"(d[30]), "+f"(d[31]),
        "+f"(d[32]), "+f"(d[33]), "+f"(d[34]), "+f"(d[35]), "+f"(d[36]), "+f"(d[37]), "+f"(d[38]), "+f"(d[39]),
        "+f"(d[40]), "+f"(d[41]), "+f"(d[42]), "+f"(d[43]), "+f"(d[44]), "+f"(d[45]), "+f"(d[46]), "+f"(d[47]),
        "+f"(d[48]), "+f"(d[49]), "+f"(d[50]), "+f"(d[51]), "+f"(d[52]), "+f"(d[53]), "+f"(d[54]), "+f"(d[55]),
        "+f"(d[56]), "+f"(d[57]), "+f"(d[58]), "+f"(d[59]), "+f"(d[60]), "+f"(d[61]), "+f"(d[62]), "+f"(d[63])
      : "l"(da), "l"(db));
}
__device__ __forceinline__ void mma_rs24_acc(float (&d)[12], uint32_t a0, uint32_t a1, uint32_t a2, uint32_t a3, uint64_t db) {
  asm volatile("{.reg .pred p; setp.ne.b32 p, 1, 0;\n"
      "wgmma.mma_async.sync.aligned.m64n24k16.f32.bf16.bf16 {"
      "%0, %1, %2, %3, %4, %5, %6, %7, %8, %9, %10, %11}, {%12, %13, %14, %15}, %16, p, 1, 1, 1;}\n"
      : "+f"(d[0]), "+f"(d[1]), "+f"(d[2]), "+f"(d[3]), "+f"(d[4]), "+f"(d[5]), "+f"(d[6]), "+f"(d[7]),
        "+f"(d[8]), "+f"(d[9]), "+f"(d[10]), "+f"(d[11])
      : "r"(a0), "r"(a1), "r"(a2), "r"(a3), "l"(db));
}

__device__ __forceinline__ uint32_t exp2_pair_poly(float t0, float t1) {
  const uint32_t w = __byte_perm(__float_as_uint(t0), __float_as_uint(t1), 0x6521);
  uint32_t y, h, r;
  asm("lop3.b32 %0, %1, 0x007F007F, %2, 0xEA;" : "=r"(y) : "r"(w), "r"(0x3F803F80u));
  asm("fma.rn.bf16x2 %0, %1, %2, %3;" : "=r"(h) : "r"(y), "r"(0x3D8A3D8Au), "r"(0x3D193D19u));
  asm("fma.rn.bf16x2 %0, %1, %2, %3;" : "=r"(h) : "r"(h), "r"(y), "r"(0x3ED53ED5u));
  asm("fma.rn.bf16x2 %0, %1, %2, %3;" : "=r"(h) : "r"(h), "r"(y), "r"(0x3EF53EF5u));
  asm("lop3.b32 %0, %1, 0x007F007F, %2, 0xE2;" : "=r"(r) : "r"(h), "r"(w));
  return r;
}
template <bool FAST, int SH>
__device__ __forceinline__ void softmax_tile(float (&s)[32], uint32_t (&p)[16], float (&o)[12], float& m0, float& m1) {
  if (FAST) {
#pragma unroll
    for (int jj = 0; jj < 8; jj++) {
      const int j = (jj + 4) & 7;
      if ((POLYMASK >> (j + SH)) & 1) {
        p[2 * j] = exp2_pair_poly(s[4 * j], s[4 * j + 1]);
        p[2 * j + 1] = exp2_pair_poly(s[4 * j + 2], s[4 * j + 3]);
      } else {
        p[2 * j] = pack_bf16(ex2(s[4 * j]), ex2(s[4 * j + 1]));
        p[2 * j + 1] = pack_bf16(ex2(s[4 * j + 2]), ex2(s[4 * j + 3]));
      }
    }
  } else {
    float n0 = m0, n1 = m1;
#pragma unroll
    for (int j = 0; j < 8; j++) {
      if ((POLYMASK >> (j + SH)) & 1) {
#pragma unroll
        for (int e = 0; e < 4; e++) s[4 * j + e] -= 384.00390625f;
      }
      n0 = fmaxf(n0, fmaxf(s[4 * j], s[4 * j + 1]));
      n1 = fmaxf(n1, fmaxf(s[4 * j + 2], s[4 * j + 3]));
    }
    n0 = fmaxf(n0, __shfl_xor_sync(0xffffffffu, n0, 1));
    n1 = fmaxf(n1, __shfl_xor_sync(0xffffffffu, n1, 1));
    n0 = fmaxf(n0, __shfl_xor_sync(0xffffffffu, n0, 2));
    n1 = fmaxf(n1, __shfl_xor_sync(0xffffffffu, n1, 2));
    const float a0 = ex2(m0 - n0), a1 = ex2(m1 - n1);
    m0 = n0; m1 = n1;
#pragma unroll
    for (int j = 0; j < 3; j++) { o[4 * j] *= a0; o[4 * j + 1] *= a0; o[4 * j + 2] *= a1; o[4 * j + 3] *= a1; }
#pragma unroll
    for (int j = 0; j < 8; j++) {
      const float f = ((POLYMASK >> (j + SH)) & 1) ? -2.f : 1.f;
      p[2 * j] = pack_bf16(f * ex2(s[4 * j] - n0), f * ex2(s[4 * j + 1] - n0));
      p[2 * j + 1] = pack_bf16(f * ex2(s[4 * j + 2] - n1), f * ex2(s[4 * j + 3] - n1));
    }
    pin(o);
  }
  pin(p);
}
__device__ __forceinline__ void mma_qk(float (&s)[32], uint64_t dq0, uint64_t dq1, uint64_t d, int hf) {
  mma_ss64_set(s, dq0, d + hf * 128);
  mma_ss64_acc(s, dq1, d + (256 + hf * 8 - NO_LBO));
}
__device__ __forceinline__ void mma_pv(float (&o)[12], const uint32_t (&p)[16], uint64_t d, int hf) {
#pragma unroll
  for (int k = 0; k < 4; k++) mma_rs24_acc(o, p[4 * k], p[4 * k + 1], p[4 * k + 2], p[4 * k + 3], d + (384 + (hf * 4 + k) * 48));
}
template <bool FAST>
__device__ __forceinline__ void attn_pass(float (&o)[12], uint64_t dq0, uint64_t dq1, uint64_t d0, int c0, bool filler, const uint8_t* kv,
                                          int bme, int bnx, const float* gp, float& g0, float& g1) {
  auto turn = [&]() { asm volatile("bar.sync %0, 256;" ::"r"(bme) : "memory"); };
  auto pass = [&]() { asm volatile("bar.arrive %0, 256;" ::"r"(bnx) : "memory"); };
  float s[32];
  uint32_t p[16];
  float m0 = -INFINITY, m1 = -INFINITY;
  uint32_t barF = BAR(B_KF) + 8 * c0;
  auto refill = [&](uint32_t bf) {
    if (filler) {
      const uint32_t c = (bf - BAR(B_KF)) >> 3;
      if (c - 1 < 28) {
        mbar_wait(bf - 8 * (B_KF - B_KE + 1));
        asm volatile("{.reg .pred p; elect.sync _|p, 0xffffffff;\n"
                     "@p mbarrier.arrive.expect_tx.shared::cta.b64 _, [%2], 12288;\n"
                     "@p cp.async.bulk.shared::cluster.global.mbarrier::complete_tx::bytes [%0], [%1], 12288, [%2];}"
                     ::"r"(SM_KV + ((c + 3) & 3) * 12288), "l"(kv + ((c + 3) & 15) * 12288), "r"(bf + 24) : "memory");
      }
    }
  };
  auto step_b = [&](uint64_t d) {
    turn(); wg_fence(); mma_pv(o, p, d, 0); mma_qk(s, dq0, dq1, d, 1); wg_commit(); pass(); wg_wait<0>(); pin(s); if (!FAST) pin(o);
    softmax_tile<FAST, 8>(s, p, o, m0, m1);
  };
  auto step_a = [&](uint64_t d, uint64_t dn) {
    mbar_wait(barF + 8);
    turn(); wg_fence(); mma_pv(o, p, d, 1); mma_qk(s, dq0, dq1, dn, 0); wg_commit(); pass(); wg_wait<0>(); pin(s); if (!FAST) pin(o);
    mbar_arrive_lane0(barF - 8 * (B_KF - B_KE));
    refill(barF);
    softmax_tile<FAST, 0>(s, p, o, m0, m1);
  };
#pragma unroll
  for (int i = 0; i < 12; i++) o[i] = 0.f;
  pin(o);
  mbar_wait(barF);
  wg_fence(); mma_qk(s, dq0, dq1, d0, 0); wg_commit(); wg_wait<0>(); pin(s);
  softmax_tile<FAST, 0>(s, p, o, m0, m1);
  const uint32_t barE = barF + 8 * 15;
  uint64_t d = d0;
#pragma unroll 1
  do {
    step_b(d);
    const uint64_t dn = (uint32_t)d == (uint32_t)d0 + 2304 ? d0 : d + 768;
    step_a(d, dn);
    d = dn;
    barF += 8;
  } while (barF != barE);
  step_b(d);
  asm volatile("ld.global.cg.f32 %0, [%1];" : "=f"(g0) : "l"(gp) : "memory");
  asm volatile("ld.global.cg.f32 %0, [%1+32];" : "=f"(g1) : "l"(gp) : "memory");
  wg_fence(); mma_pv(o, p, d, 1); wg_commit(); wg_wait<0>(); pin(o);
  mbar_arrive_lane0(c0 ? BAR(B_AD) : BAR(B_KE + 15));
  refill(barE);
}

struct Args {
  const __nv_bfloat16 *x, *w1, *b1, *b2, *gate_w;
  uint64_t zero;
};

__global__ void __launch_bounds__(640, 1)
fused_kernel(const __grid_constant__ CUtensorMap tmX, const __grid_constant__ CUtensorMap tmWqkv,
             const __grid_constant__ CUtensorMap tmW1, const __grid_constant__ CUtensorMap tmW2,
             const __grid_constant__ CUtensorMap tmWo, const __grid_constant__ CUtensorMap tmH,
             const __grid_constant__ CUtensorMap tmHst, const __grid_constant__ CUtensorMap tmO,
             const __grid_constant__ CUtensorMap tmOut, const Args a) {
  extern __shared__ uint8_t smem_raw[];
  if ((uint32_t)__cvta_generic_to_shared(smem_raw) != SB) return;
  const int b = blockIdx.x;
  const int lane = threadIdx.x & 31;
  const int warp = __shfl_sync(0xffffffffu, threadIdx.x >> 5, 0);
  const int wg = warp >> 2, wq = warp & 3;
  const int ti = (b >> 5) * 4 + (b & 3);
  const int tj = ((b >> 4) & 1) * 4 + ((b >> 2) & 3);
  const int mtA = (ti >> 2) * 8 + (ti & 3);

  auto load_x = [&](int kb) {
    const uint32_t br = BAR(B_FX) + 8 * kb, dst = SM_X + kb * 16384;
    mbar_expect(br, 16384);
    tma2d(dst, &tmX, kb * 64, mtA * 64, br);
    tma2d(dst + 8192, &tmX, kb * 64, mtA * 64 + 256, br);
  };
  auto load_w = [&](int s) {
    const uint32_t br = BAR(B_FW) + 8 * s, dst = SM_W + (s & 3) * 16384;
    const int r = s >= 10, kb = s - 10 * r;
    mbar_expect(br, 16384);
    tma2d(dst, &tmWqkv, tj * 240 + r * 112, kb * 64, br);
    tma2d(dst + 8192, &tmWqkv, tj * 240 + r * 112 + 64, kb * 64, br);
  };
  if (warp == 16) {
    if (elect_one()) {
#pragma unroll
      for (int i = 0; i < 3; i++) {
        asm volatile("mbarrier.init.shared::cta.b64 [%0], 1;" ::"r"(BAR(B_FX + i)) : "memory");
        asm volatile("mbarrier.init.shared::cta.b64 [%0], 1;" ::"r"(BAR(B_FW + i)) : "memory");
      }
      asm volatile("fence.mbarrier_init.release.cluster;" ::: "memory");
#pragma unroll 1
      for (int i = 0; i < 3; i++) { load_x(i); load_w(i); }
    }
  } else if (warp == 18) {
    if (elect_one()) {
#pragma unroll
      for (int i = 3; i < 30; i++)
        if (i < 10 || i >= 13) asm volatile("mbarrier.init.shared::cta.b64 [%0], 1;" ::"r"(BAR(B_FX + i)) : "memory");
      asm volatile("fence.mbarrier_init.release.cluster;" ::: "memory");
    }
  } else if (warp < 18) {
    if (elect_one()) {
      const int w = warp == 17 ? 16 : warp;
      const uint32_t base = w < 6 ? BAR(0) + w * 80 : BAR(B_KF) + (w - 6) * 88;
      const uint32_t cnt = w < 2 ? 8 : w < 6 ? 16 : 1;
#pragma unroll
      for (int i = 0; i < 10; i++) asm volatile("mbarrier.init.shared::cta.b64 [%0], %1;" ::"r"(base + 8 * i), "r"(cnt) : "memory");
      if (w >= 6) asm volatile("mbarrier.init.shared::cta.b64 [%0], 1;" ::"r"(base + 80) : "memory");
      asm volatile("fence.mbarrier_init.release.cluster;" ::: "memory");
    }
  }
  __syncthreads();

  if (wg < 4) {
    const int c = lane & 3;
    {
      const int wm = wg & 1, wn = wg >> 1;
      float acc[64];
      uint64_t da = (DESC_A128 | ((SM_X + wm * 8192) >> 4)) + a.zero;
      uint32_t br = BAR(0) + 80 * wn;
#pragma unroll 1
      for (int kb = 0; kb < 10; kb++) {
        const uint64_t db = DESC_B128 | ((SM_W >> 4) + ((kb + 2 * wn) & 3) * 1024);
        if (kb == 0 && wn == 1) asm volatile("bar.sync 7, 288;" ::: "memory");
        if (kb == 8 && warp == 0) asm volatile("bar.arrive 7, 288;" ::: "memory");
        mbar_wait(BAR(B_FX) + 8 * kb);
        mbar_wait(br + 8 * B_FW);
        wg_fence();
        mma_st128_sel(acc, da, db, kb);
#pragma unroll
        for (int k = 1; k < 4; k++) mma_st128_acc(acc, da + 2 * k, db + 128 * k);
        wg_commit();
        wg_wait<1>();
        if (kb > 0) mbar_arrive_lane0(br - 8);
        da += 1024; br += 8;
      }
      wg_wait<0>(); pin(acc);
      mbar_arrive_lane0(br - 8);
      if (wn) {
#pragma unroll
        for (int i = 0; i < 60; i++) acc[i] = acc[i + 4];
      }
      pin(acc);
      asm volatile("setmaxnreg.dec.sync.aligned.u32 88;");
      const int wr = 2 * tj + wn;
      const int r16 = (mtA + 4 * wm) * 4 + wq;
      const bool pl0 = (POLYMASK >> ((2 * r16) & 15)) & 1, pl1 = (POLYMASK >> ((2 * r16 + 1) & 15)) & 1;
      constexpr float QS = 0.32259642f;
#pragma unroll
      for (int pp = 0; pp < 3; pp++) {
        const int gh = 6 * wr + 2 * pp, ty = gh >> 5, h = gh & 31;
        const float sa0 = ty == 0 ? QS : (ty == 2 && pl0 ? -0.5f : 1.f), sa1 = ty == 0 ? QS : (ty == 2 && pl1 ? -0.5f : 1.f);
        const float sb0 = ty == 0 ? 0.5f * QS : sa0, sb1 = ty == 0 ? 0.5f * QS : sa1;
        uint32_t pad0 = ty == 0 ? 0x3B004340u : (ty == 1 ? (pl0 ? 0x3F803F80u : 0u) : (pl0 ? 0xBF00u : 0x3F80u));
        uint32_t pad1 = ty == 0 ? 0x3B004340u : (ty == 1 ? (pl1 ? 0x3F803F80u : 0u) : (pl1 ? 0xBF00u : 0x3F80u));
        if (c & 1) { pad0 = 0; pad1 = 0; }
        const uint32_t hs = ty == 0 ? 98304u : 196608u;
        const uint32_t g = (2 * r16) & 15, blk = (r16 >> 3) * (ty == 0 ? 6144u : 12288u);
        const uint32_t o0 = ty == 2 ? 6144 + (g >> 1) * 768 : g * 256;
        const uint32_t o1 = ty == 2 ? 256 : 128, o2 = ty == 2 ? 512 : 4096 + (g & 7) * 256 + (g >> 3) * 128 - g * 256;
        const uint32_t rs = ty == 2 ? 128 : 256;
        uint8_t* pe = (ty == 0 ? g_Q : g_KV) + (h * hs + blk + o0 + lane * 4);
        const float* v = &acc[20 * pp];
        const uint32_t mid0 = pack_bf16(v[8] * sb0, v[9] * sb0), mid1 = pack_bf16(v[10] * sb1, v[11] * sb1);
        *(uint32_t*)(pe) = pack_bf16(v[0] * sa0, v[1] * sa0);
        *(uint32_t*)(pe + o1) = pack_bf16(v[4] * sa0, v[5] * sa0);
        *(uint32_t*)(pe + o2) = c < 2 ? mid0 : pad0;
        *(uint32_t*)(pe + rs) = pack_bf16(v[2] * sa1, v[3] * sa1);
        *(uint32_t*)(pe + (rs + o1)) = pack_bf16(v[6] * sa1, v[7] * sa1);
        *(uint32_t*)(pe + (rs + o2)) = c < 2 ? mid1 : pad1;
        if (!wn) __nanosleep(200);
        pe += hs;
        *(uint32_t*)(pe) = pack_bf16(v[12] * sa0, v[13] * sa0);
        *(uint32_t*)(pe + o1) = pack_bf16(v[16] * sa0, v[17] * sa0);
        *(uint32_t*)(pe + o2) = c < 2 ? pad0 : mid0;
        *(uint32_t*)(pe + rs) = pack_bf16(v[14] * sa1, v[15] * sa1);
        *(uint32_t*)(pe + (rs + o1)) = pack_bf16(v[18] * sa1, v[19] * sa1);
        *(uint32_t*)(pe + (rs + o2)) = c < 2 ? pad1 : mid1;
        if (pp < 2 && !wn) __nanosleep(200);
        const float q0 = v[8] * v[8] + v[9] * v[9], q1 = v[10] * v[10] + v[11] * v[11];
        const float e0 = v[0] * v[0] + v[1] * v[1] + v[4] * v[4] + v[5] * v[5];
        const float e1 = v[2] * v[2] + v[3] * v[3] + v[6] * v[6] + v[7] * v[7];
        const float n0 = v[12] * v[12] + v[13] * v[13] + v[16] * v[16] + v[17] * v[17];
        const float n1 = v[14] * v[14] + v[15] * v[15] + v[18] * v[18] + v[19] * v[19];
        const float k0 = (c < 2 ? e0 : n0) + q0 + __shfl_xor_sync(0xffffffffu, c < 2 ? n0 : e0, 2);
        const float k1 = (c < 2 ? e1 : n1) + q1 + __shfl_xor_sync(0xffffffffu, c < 2 ? n1 : e1, 2);
        const float kk = ((c & 1) ? k1 : k0) + __shfl_xor_sync(0xffffffffu, (c & 1) ? k0 : k1, 1);
        const uint32_t kb = __float_as_uint(kk);
        const uint32_t me = __reduce_max_sync(0xffffffffu, c < 2 ? kb : 0u);
        const uint32_t mo = __reduce_max_sync(0xffffffffu, c < 2 ? 0u : kb);
        if (lane < 2) g_nrm[(gh + lane) * 128 + r16] = __uint_as_float(lane ? mo : me);
      }
      bar_wg(1 + wg);
      if (wq == 0 && elect_one()) { mbar_wait(BAR(B_EP)); flag_add(C_QKV + wr); }
    }
    const int head = b >> 2, rb = b & 3;
    const uint8_t* kv = g_KV + head * 196608;
    if (warp == 1) {
      uint32_t epoch;
      mbar_wait(BAR(B_EP));
      asm volatile("ld.shared.u32 %0, [%1];" : "=r"(epoch) : "r"(SM_EPOCH) : "memory");
      const int idx = (lane & 3) == 3 ? C_G : C_QKV + ((lane & 3) * 32 + head) / 6;
      const uint32_t target = epoch * ((lane & 3) == 3 ? 256 : 32);
      mbar_wait(BAR(B_XF));
      for (int n = 0; n < 2000000; n++) {
        uint32_t v;
        asm volatile("ld.relaxed.gpu.global.u32 %0, [%1];" : "=r"(v) : "l"(&g_cnt[idx * 32]) : "memory");
        if (__all_sync(0xffffffffu, (int32_t)(v - target) >= 0)) break;
      }
      fence_acquire();
      const uint4 kn = __ldcg((const uint4*)&g_nrm[(32 + head) * 128] + lane);
      const uint4 vn = __ldcg((const uint4*)&g_nrm[(64 + head) * 128] + lane);
      const float qn = __ldcg(&g_nrm[head * 128 + rb * 32 + lane]);
      if (elect_one()) {
        const uint8_t* q = g_Q + (head * 98304 + rb * 24576);
        fence_async_g();
        mbar_expect(BAR(B_KF), 24576);
        bulk_load(SM_KV, kv, 12288, BAR(B_KF));
        bulk_load(SM_Q, q, 12288, BAR(B_KF));
      }
      __syncwarp();
      const uint32_t km = __reduce_max_sync(0xffffffffu, max(max(kn.x, kn.y), max(kn.z, kn.w)));
      const uint32_t vm = __reduce_max_sync(0xffffffffu, max(max(vn.x, vn.y), max(vn.z, vn.w)));
      const float k2 = (__uint_as_float(vm) <= 1e30f) ? __uint_as_float(km) * (0.32259642f * 0.32259642f) : INFINITY;
      const uint32_t ok = __ballot_sync(0xffffffffu, qn * k2 <= 3600.f);
      if (lane == 0) asm volatile("st.shared.u32 [%0], %1;" ::"r"(SM_FAST), "r"(ok) : "memory");
    }
    asm volatile("bar.sync 6, 512;" ::: "memory");
    if (warp == FILLER) {
      mbar_wait(BAR(B_KF));
      if (elect_one()) {
        fence_async_g();
        mbar_expect(BAR(B_KF + 1), 12288);
        bulk_load(SM_KV + 12288, kv + 12288, 12288, BAR(B_KF + 1));
        mbar_expect(BAR(B_KF + 2), 12288);
        bulk_load(SM_KV + 24576, kv + 24576, 12288, BAR(B_KF + 2));
      }
      __syncwarp();
    }
    uint32_t fastm;
    asm volatile("ld.shared.u32 %0, [%1];" : "=r"(fastm) : "r"(SM_FAST) : "memory");
    const bool fast0 = __all_sync(0xffffffffu, ((fastm >> (4 * wg)) & 15) == 15);
    const bool fast1 = __all_sync(0xffffffffu, ((fastm >> (16 + 4 * wg)) & 15) == 15);
    const uint64_t d0 = (DESC_C | (SM_KV >> 4)) + a.zero;
    if (wg == 3) asm volatile("bar.arrive 8, 256;" ::: "memory");
#pragma unroll 1
    for (int ps = 0; ps < 2; ps++) {
      const int mt = rb * 8 + ps * 4 + wg;
      const int row = mt * 64 + wq * 16 + (lane >> 2);
      const uint32_t qa = (SM_Q + ps * 61440 + (wg >> 1) * 6144) >> 4;
      const uint64_t dq0 = DESC_C | (qa + (wg & 1) * 128), dq1 = (DESC_C - NO_LBO) | (qa + 256 + (wg & 1) * 8);
      float o[12], g0, g1;
      if (ps ? fast1 : fast0) attn_pass<true>(o, dq0, dq1, d0, ps * 16, warp == FILLER, kv, 8 + wg, 8 + ((wg + 1) & 3), &g_gate[row], g0, g1);
      else attn_pass<false>(o, dq0, dq1, d0, ps * 16, warp == FILLER, kv, 8 + wg, 8 + ((wg + 1) & 3), &g_gate[row], g0, g1);
      const int par = head & 1;
      const int src = (lane & ~3) | (par ? 0 : 2);
      const float l0 = __shfl_sync(0xffffffffu, o[8], src), l1 = __shfl_sync(0xffffffffu, o[10], src);
      const float i0 = __fdividef(g0, l0), i1 = __fdividef(g1, l1);
      const uint32_t st = (qa << 4) + (wg & 1) * 2048 + wq * 512;
      const uint32_t sw = st + (lane >> 2) * 40 + (c + 2 * par) * 4;
      const int lr = lane / 5, lc = lane - lr * 5;
      uint2* dst = (uint2*)(g_O + (mt * 64 + wq * 16 + lr) * 640 + head * 20) + lc;
#pragma unroll
      for (int hf = 0; hf < 2; hf++) {
        const float iv = hf ? i1 : i0;
        if (hf) __syncwarp();
        asm volatile("st.shared.u32 [%0], %1;" ::"r"(sw), "r"(pack_bf16(o[2 * hf] * iv, o[2 * hf + 1] * iv)) : "memory");
        asm volatile("st.shared.u32 [%0], %1;" ::"r"(sw + 16), "r"(pack_bf16(o[4 + 2 * hf] * iv, o[5 + 2 * hf] * iv)) : "memory");
        if ((c >> 1) == par)
          asm volatile("st.shared.u32 [%0], %1;" ::"r"(sw + (par ? -16 : 32)), "r"(pack_bf16(o[8 + 2 * hf] * iv, o[9 + 2 * hf] * iv)) : "memory");
        __syncwarp();
        uint2 v0, v1;
        asm volatile("ld.shared.v2.u32 {%0, %1}, [%2];" : "=r"(v0.x), "=r"(v0.y) : "r"(st + lane * 8) : "memory");
        asm volatile("ld.shared.v2.u32 {%0, %1}, [%2];" : "=r"(v1.x), "=r"(v1.y) : "r"(st + 240 + lane * 8) : "memory");
        if (lane < 30) dst[hf * 8 * 160] = v0;
        if (lane < 10) dst[(hf * 8 + 6) * 160] = v1;
      }
      if (ps == 0) {
        __syncwarp();
        mbar_arrive_lane0(BAR(B_OD));
      } else {
        bar_wg(1 + wg);
        if (wq == 0 && elect_one()) asm volatile("red.release.gpu.global.add.u32 [%0], 4;" ::"l"(&g_cnt[(C_O + mt) * 32 + head]) : "memory");
      }
    }
    if (wg == 0) asm volatile("bar.sync 8, 256;" ::: "memory");
    if (warp == 1) {
      uint32_t epoch;
      asm volatile("ld.shared.u32 %0, [%1];" : "=r"(epoch) : "r"(SM_EPOCH) : "memory");
      mbar_wait(BAR(B_AD));
      const uint32_t lo = (min(lane, 9) * 16) / 5, hi = (min(lane, 9) * 16 + 15) / 5;
      const uint32_t need = lane < 10 ? (0xffffffffu >> (31 - hi)) & (0xffffffffu << lo) : 0u;
      uint32_t todo = 0x3ff;
      int i = 0;
      for (int n = 0; n < 2000000 && todo; n++) {
        uint32_t v;
        asm volatile("ld.relaxed.gpu.global.u32 %0, [%1];" : "=r"(v) : "l"(&g_cnt[(C_O + mtA + 4) * 32 + lane]) : "memory");
        const uint32_t done = __ballot_sync(0xffffffffu, v == 4 * epoch);
        uint32_t go = __ballot_sync(0xffffffffu, (need & ~done) == 0) & todo;
        todo &= ~go;
        if (go) {
          fence_acquire(); fence_async_g();
          do {
            const int kb = __ffs(go) - 1;
            go &= go - 1;
            if (i == 7) mbar_wait(BAR(B_OF));
            if (elect_one()) {
              asm volatile("st.shared.u32 [%0], %1;" ::"r"(SM_ORD + 4 * i), "r"(kb) : "memory");
              mbar_expect(BAR(B_OB) + 8 * i, 8192);
              tma2d(i < 7 ? SB + i * 8192 : SM_OA + (i - 6) * 8192, &tmO, kb * 64, mtA * 64 + 256, BAR(B_OB) + 8 * i);
            }
            __syncwarp();
            i++;
          } while (go);
        }
      }
    }
  } else {
#define T0 (wq == 0 && elect_one())
    const int c = lane & 3;
    auto load_w1 = [&](int s) {
      const uint32_t dst = SM_W + (s & 3) * 12288, br = BAR(B_F1) + 8 * s;
      const int pc = s >= 10, kb = s < 10 ? s : s < 17 ? s - 7 : s - 17;
      mbar_expect(br, 12288);
#pragma unroll
      for (int q = 0; q < 3; q++) tma2d(dst + q * 4096, &tmW1, tj * 192 + pc * 96 + q * 32, kb * 64, br);
    };
    auto load_ffn2 = [&](int s) {
      const uint32_t dst = SM_G + (s & 3) * 28672, br = BAR(B_F2) + 8 * s;
      mbar_expect(br, 28672);
      tma2d(dst, &tmH, s * 64, mtA * 64, br);
      tma2d(dst + 8192, &tmH, s * 64, mtA * 64 + 256, br);
#pragma unroll
      for (int q = 0; q < 3; q++) tma2d(dst + 16384 + q * 4096, &tmW2, tj * 80 + q * 32, s * 64, br);
    };
    if (wq == 0) {
      if (elect_one()) {
#pragma unroll 1
        for (int s = 3; s < 20; s++) {
          if (s < 10) {
            if (s == 3) mbar_wait(BAR(B_FW));
            load_x(s);
          }
          if (s >= 4) mbar_wait(BAR(B_EW) + 8 * (s - 4));
          load_w(s);
        }
        mbar_wait(BAR(B_EW + 16)); load_w1(0);
        mbar_wait(BAR(B_EW + 17)); load_w1(1);
        mbar_wait(BAR(B_EW + 18)); load_w1(2); load_w1(3);
      }
    } else if (wq < 3) {
      const uint4* gw = (const uint4*)a.gate_w;
      const uint4 w0 = __ldg(gw + lane), w1 = __ldg(gw + 32 + lane), w2 = lane < 16 ? __ldg(gw + 64 + lane) : make_uint4(0, 0, 0, 0);
#pragma unroll 1
      for (int it = 0; it < 2; it++) {
        float z[4];
        const int rr = tj * 16 + (wq - 1) * 8 + it * 4;
        const int row = (mtA + (rr >> 6) * 4) * 64 + (rr & 63);
#pragma unroll
        for (int q = 0; q < 4; q++) {
          const uint4* xr = (const uint4*)(a.x + (row + q) * 640);
          const uint4 x0 = __ldg(xr + lane), x1 = __ldg(xr + 32 + lane), x2 = lane < 16 ? __ldg(xr + 64 + lane) : make_uint4(0, 0, 0, 0);
          auto dot = [](uint4 u, uint4 w) {
            return bf_lo(u.x) * bf_lo(w.x) + bf_hi(u.x) * bf_hi(w.x) + bf_lo(u.y) * bf_lo(w.y) + bf_hi(u.y) * bf_hi(w.y) +
                   bf_lo(u.z) * bf_lo(w.z) + bf_hi(u.z) * bf_hi(w.z) + bf_lo(u.w) * bf_lo(w.w) + bf_hi(u.w) * bf_hi(w.w);
          };
          z[q] = dot(x0, w0) + dot(x1, w1) + dot(x2, w2);
        }
#pragma unroll
        for (int q = 0; q < 4; q++) {
#pragma unroll
          for (int d = 16; d > 0; d >>= 1) z[q] += __shfl_xor_sync(0xffffffffu, z[q], d);
        }
        const float zz = lane == 0 ? z[0] : lane == 1 ? z[1] : lane == 2 ? z[2] : z[3];
        if (lane < 4) g_gate[row + lane] = 1.f / (1.f + __expf(-zz));
      }
      __syncwarp();
      if (elect_one()) flag_add(C_G);
    } else if (elect_one()) {
      uint32_t v;
      asm volatile("ld.relaxed.gpu.global.u32 %0, [%1];" : "=r"(v) : "l"(&g_cnt[C_DONE * 32]) : "memory");
      asm volatile("st.shared.u32 [%0], %1;" ::"r"(SM_EPOCH), "r"((v >> 7) + 1) : "memory");
      asm volatile("mbarrier.arrive.shared::cta.b64 _, [%0];" ::"r"(BAR(B_EP)) : "memory");
      mbar_wait_slow(BAR(B_FW + 9));
      l2_prefetch((const uint8_t*)a.w1 + b * 15360, 15360);
    }
    __syncwarp();
    bar_wg4();
    asm volatile("setmaxnreg.inc.sync.aligned.u32 128;");
    mbar_wait(BAR(B_EP));
    uint32_t epoch;
    asm volatile("ld.shared.u32 %0, [%1];" : "=r"(epoch) : "r"(SM_EPOCH) : "memory");
    mbar_wait(BAR(B_EW + 19));
#pragma unroll 1
    for (int pc = 0; pc < 2; pc++) {
      float acc0[48], acc1[48];
#pragma unroll 1
      for (int kb = 0; kb < 10; kb++) {
        const int s = pc * 10 + kb;
        const int xs = pc == 0 ? kb : kb < 7 ? kb + 3 : kb - 2;
        const uint64_t da = DESC_A128 | ((SM_X >> 4) + xs * 1024), db = DESC_B64 | ((SM_W >> 4) + (s & 3) * 768);
        if (s >= 17) mbar_wait(BAR(B_RX - 17) + 8 * s);
        mbar_wait(BAR(B_F1) + 8 * s);
        wg_fence();
        mma_st96_sel(acc0, da, db, kb); mma_st96_sel(acc1, da + 512, db, kb);
#pragma unroll
        for (int k = 1; k < 4; k++) { mma_st96_acc(acc0, da + 2 * k, db + 64 * k); mma_st96_acc(acc1, da + 512 + 2 * k, db + 64 * k); }
        wg_commit();
        wg_wait<1>();
        bar_wg4();
        if (wq == 0 && s == 12) mbar_wait(BAR(B_KF));
        if (T0) {
          if (s >= 1 && s < 17) load_w1(s + 3);
          if (s == 3) { asm volatile("mbarrier.arrive.shared::cta.b64 _, [%0];" ::"r"(BAR(B_XF)) : "memory"); }
          if (s == 12) {
            fence_async_g();
            mbar_expect(BAR(B_KF + 3), 24576);
            bulk_load(SM_KV + 36864, g_KV + ((b >> 2) * 196608 + 36864), 12288, BAR(B_KF + 3));
            bulk_load(SM_Q + 61440, g_Q + ((b >> 2) * 98304 + (b & 3) * 24576 + 12288), 12288, BAR(B_KF + 3));
          }
          if (s >= 13 && s < 16) {
            const uint32_t br = BAR(B_RX - 13) + 8 * s, dst = SM_X + (s - 8) * 16384;
            mbar_expect(br, 16384);
            tma2d(dst, &tmX, (s - 13) * 64, mtA * 64, br);
            tma2d(dst + 8192, &tmX, (s - 13) * 64, mtA * 64 + 256, br);
          }
        }
      }
      wg_wait<0>(); pin(acc0); pin(acc1);
      uint32_t bb[12];
#pragma unroll
      for (int j = 0; j < 12; j++) bb[j] = __ldg((const uint32_t*)(a.b1 + tj * 192 + pc * 96) + c + 4 * j);
      const int rl = wq * 16 + (lane & 15);
      const uint32_t sa = SM_STG + rl * 64;
      auto half = [&](float (&acc)[48], int row) {
        if (T0) asm volatile("cp.async.bulk.wait_group.read 0;" ::: "memory");
        bar_wg4();
#pragma unroll
        for (int jp = 0; jp < 6; jp++) {
          uint32_t r[4];
#pragma unroll
          for (int e = 0; e < 4; e++) {
            uint32_t h = pack_bf16(acc[8 * jp + 2 * e], acc[8 * jp + 2 * e + 1]);
            asm("fma.rn.relu.bf16x2 %0, %1, %2, %3;" : "=r"(h) : "r"(h), "r"(0x3F803F80u), "r"(bb[2 * jp + (e >> 1)]));
            asm("mul.rn.bf16x2 %0, %1, %1;" : "=r"(r[e]) : "r"(h));
          }
          const uint32_t ch = ((2 * jp) & 3) + (lane >> 4);
          asm volatile("stmatrix.sync.aligned.m8n8.x4.shared.b16 [%0], {%1, %2, %3, %4};"
                       ::"r"(sa + (jp >> 1) * 4096 + ((ch ^ ((rl >> 1) & 3)) << 4)), "r"(r[0]), "r"(r[1]), "r"(r[2]), "r"(r[3]) : "memory");
        }
        fence_async_s();
        bar_wg4();
        if (T0) {
#pragma unroll
          for (int q = 0; q < 3; q++) tma2d_store(&tmHst, tj * 192 + pc * 96 + q * 32, row, SM_STG + q * 4096);
          asm volatile("cp.async.bulk.commit_group;" ::: "memory");
        }
      };
      half(acc0, mtA * 64);
      half(acc1, mtA * 64 + 256);
    }
    if (T0) {
      asm volatile("cp.async.bulk.wait_group 0;" ::: "memory");
      flag_add(C_H + ti);
      flag_wait(C_H + ti, epoch * 8);
      fence_acquire(); fence_async_g();
      load_ffn2(0); load_ffn2(1); load_ffn2(2); load_ffn2(3);
    }
    __syncwarp();
    bar_wg4();
    float acc0[40], acc1[40];
    bool published = false;
    auto publish = [&]() {
      asm volatile("fence.release.gpu;" ::: "memory");
#pragma unroll
      for (int w = 0; w < 4; w++)
        asm volatile("red.relaxed.gpu.global.add.u32 [%0], 4;" ::"l"(&g_cnt[(C_O + (b & 3) * 8 + w) * 32 + (b >> 2)]) : "memory");
    };
#pragma unroll 1
    for (int s = 0; s < 24; s++) {
      const uint32_t st = (SM_G >> 4) + (s & 3) * 1792;
      const uint64_t da = DESC_A128 | st, db = DESC_B64 | (st + 1024);
      mbar_wait(BAR(B_F2) + 8 * s);
      wg_fence();
      mma_st80_sel(acc0, da, db, s); mma_st80_sel(acc1, da + 512, db, s);
#pragma unroll
      for (int k = 1; k < 4; k++) {
        wg_commit(); wg_wait<0>();
        __nanosleep(10);
        wg_fence();
        mma_st80_acc(acc0, da + 2 * k, db + 64 * k); mma_st80_acc(acc1, da + 512 + 2 * k, db + 64 * k);
      }
      wg_commit(); wg_wait<0>();
      bar_wg4();
      if (wq == 0) {
        if (elect_one()) {
          if (s < 20) load_ffn2(s + 4);
          else {
#pragma unroll 1
            for (int kb = s == 20 ? 0 : 2 * s - 39; kb < (s == 23 ? 10 : 2 * s - 37); kb++) {
              const uint32_t br = BAR(B_WF) + 8 * kb;
              mbar_expect(br, 12288);
#pragma unroll
              for (int q = 0; q < 3; q++) tma2d(SM_WO + kb * 12288 + q * 4096, &tmWo, tj * 80 + q * 32, kb * 64, br);
            }
          }
        }
        __syncwarp();
        if (!published && __all_sync(0xffffffffu, mbar_test(BAR(B_OD)))) {
          published = true;
          if (elect_one()) publish();
        }
      }
    }
    pin(acc0); pin(acc1);
    if (wq == 0) {
      if (!published && elect_one()) { mbar_wait_slow(BAR(B_OD)); publish(); }
      __syncwarp();
      for (int n = 0; n < 2000000; n++) {
        uint32_t v;
        asm volatile("ld.relaxed.gpu.global.u32 %0, [%1];" : "=r"(v) : "l"(&g_cnt[(C_O + mtA) * 32 + lane]) : "memory");
        if (__all_sync(0xffffffffu, v == 4 * epoch)) break;
      }
      fence_acquire(); fence_async_g();
      if (elect_one()) {
#pragma unroll
        for (int kb = 0; kb < 4; kb++) {
          mbar_expect(BAR(B_OA + kb), 8192);
          tma2d(SM_OA + kb * 8192, &tmO, kb * 64, mtA * 64, BAR(B_OA + kb));
        }
      }
    }
    __syncwarp();
    const int rowA = mtA * 64 + wq * 16 + (lane >> 2);
    {
      const float u0 = 1.f - __ldcg(&g_gate[rowA]), u1 = 1.f - __ldcg(&g_gate[rowA + 8]);
      const float u2 = 1.f - __ldcg(&g_gate[rowA + 256]), u3 = 1.f - __ldcg(&g_gate[rowA + 264]);
      const uint32_t* b2 = (const uint32_t*)(a.b2 + tj * 80) + c;
#pragma unroll
      for (int j = 0; j < 10; j++) {
        const uint32_t bb = __ldg(b2 + j * 4);
        const float bl = bf_lo(bb), bh = bf_hi(bb);
        acc0[4 * j] = (acc0[4 * j] + bl) * u0; acc0[4 * j + 1] = (acc0[4 * j + 1] + bh) * u0;
        acc0[4 * j + 2] = (acc0[4 * j + 2] + bl) * u1; acc0[4 * j + 3] = (acc0[4 * j + 3] + bh) * u1;
        acc1[4 * j] = (acc1[4 * j] + bl) * u2; acc1[4 * j + 1] = (acc1[4 * j + 1] + bh) * u2;
        acc1[4 * j + 2] = (acc1[4 * j + 2] + bl) * u3; acc1[4 * j + 3] = (acc1[4 * j + 3] + bh) * u3;
      }
      pin(acc0); pin(acc1);
    }
    if (wq == 0) mbar_wait_slow(BAR(B_KE + 28));
    bar_wg4();
    const uint64_t dw = (DESC_B64 | (SM_WO >> 4)) + a.zero;
    auto store_out = [&](float (&acc)[40], int row) {
      const uint32_t sa = SM_OA + (wq * 16 + (lane & 15)) * 160 + (lane >> 4) * 16;
#pragma unroll
      for (int jp = 0; jp < 5; jp++)
        asm volatile("stmatrix.sync.aligned.m8n8.x4.shared.b16 [%0], {%1, %2, %3, %4};"
                     ::"r"(sa + jp * 32), "r"(pack_bf16(acc[8 * jp], acc[8 * jp + 1])), "r"(pack_bf16(acc[8 * jp + 2], acc[8 * jp + 3])),
                       "r"(pack_bf16(acc[8 * jp + 4], acc[8 * jp + 5])), "r"(pack_bf16(acc[8 * jp + 6], acc[8 * jp + 7])) : "memory");
      fence_async_s();
      bar_wg4();
      if (T0) {
        tma2d_store(&tmOut, tj * 80, row, SM_OA);
        asm volatile("cp.async.bulk.commit_group;" ::: "memory");
      }
    };
#pragma unroll 1
    for (int kb = 0; kb < 10; kb++) {
      const uint64_t da = DESC_A128 | ((SM_OA >> 4) + (kb & 3) * 512), db = dw + kb * 768;
      mbar_wait(BAR(B_WF) + 8 * kb);
      mbar_wait(BAR(B_OA) + 8 * kb);
      wg_fence();
#pragma unroll
      for (int k = 0; k < 4; k++) mma_st80_acc(acc0, da + 2 * k, db + 64 * k);
      wg_commit(); wg_wait<0>();
      if (kb < 6) {
        bar_wg4();
        if (T0) {
          mbar_expect(BAR(B_OA + 4) + 8 * kb, 8192);
          tma2d(SM_OA + (kb & 3) * 8192, &tmO, (kb + 4) * 64, mtA * 64, BAR(B_OA + 4) + 8 * kb);
        }
      }
    }
    pin(acc0);
    bar_wg4();
    store_out(acc0, mtA * 64);
    if (T0) {
      asm volatile("cp.async.bulk.wait_group.read 0;" ::: "memory");
      asm volatile("mbarrier.arrive.shared::cta.b64 _, [%0];" ::"r"(BAR(B_OF)) : "memory");
      mbar_wait_slow(BAR(B_AD));
    }
    __syncwarp();
    bar_wg4();
    {
#pragma unroll 1
      for (int i = 0; i < 10; i++) {
        mbar_wait(BAR(B_OB) + 8 * i);
        uint32_t kb;
        asm volatile("ld.shared.u32 %0, [%1];" : "=r"(kb) : "r"(SM_ORD + 4 * i) : "memory");
        kb = __shfl_sync(0xffffffffu, kb, 0);
        const uint64_t da = DESC_A128 | ((i < 7 ? SB + i * 8192 : SM_OA + (i - 6) * 8192) >> 4), db = dw + kb * 768;
        wg_fence();
#pragma unroll
        for (int k = 0; k < 4; k++) mma_st80_acc(acc1, da + 2 * k, db + 64 * k);
        wg_commit();
      }
      wg_wait<0>(); pin(acc1);
    }
    bar_wg4();
    store_out(acc1, mtA * 64 + 256);
    if (T0) asm volatile("cp.async.bulk.wait_group.read 0;" ::: "memory");
    if (T0) asm volatile("red.relaxed.gpu.global.add.u32 [%0], 1;" ::"l"(&g_cnt[C_DONE * 32]) : "memory");
  }
}

typedef CUresult (*EncodeFn)(CUtensorMap*, CUtensorMapDataType, cuuint32_t, void*, const cuuint64_t*, const cuuint64_t*,
                             const cuuint32_t*, const cuuint32_t*, CUtensorMapInterleave, CUtensorMapSwizzle,
                             CUtensorMapL2promotion, CUtensorMapFloatOOBfill);

void make_map(EncodeFn enc, CUtensorMap* m, const void* p, int rows, int cols, int box_cols, int box_rows = 64) {
  const cuuint64_t dims[2] = {(cuuint64_t)cols, (cuuint64_t)rows};
  const cuuint64_t strides[1] = {(cuuint64_t)cols * 2};
  const cuuint32_t box[2] = {(cuuint32_t)box_cols, (cuuint32_t)box_rows};
  const cuuint32_t es[2] = {1, 1};
  enc(m, CU_TENSOR_MAP_DATA_TYPE_BFLOAT16, 2, const_cast<void*>(p), dims, strides, box, es, CU_TENSOR_MAP_INTERLEAVE_NONE,
      box_cols == 64 ? CU_TENSOR_MAP_SWIZZLE_128B : box_cols == 32 ? CU_TENSOR_MAP_SWIZZLE_64B : CU_TENSOR_MAP_SWIZZLE_NONE, CU_TENSOR_MAP_L2_PROMOTION_L2_128B,
      CU_TENSOR_MAP_FLOAT_OOB_FILL_NONE);
}

}

extern "C" void kernel_launch(void* const* d_in, const int* in_sizes, int n_in, void* d_out, int out_size) {
  static EncodeFn enc = nullptr;
  static void *pH = nullptr, *pO = nullptr;
  if (!enc) {
    cudaDriverEntryPointQueryResult qr;
    cudaGetDriverEntryPoint("cuTensorMapEncodeTiled", (void**)&enc, cudaEnableDefault, &qr);
    cudaGetSymbolAddress(&pH, g_H);
    cudaGetSymbolAddress(&pO, g_O);
    cudaFuncSetAttribute(fused_kernel, cudaFuncAttributeMaxDynamicSharedMemorySize, SM_BYTES);
  }
  CUtensorMap tmX, tmWqkv, tmW1, tmW2, tmWo, tmH, tmHst, tmO, tmOut;
  make_map(enc, &tmX, d_in[0], 2048, 640, 64);
  make_map(enc, &tmWqkv, d_in[1], 640, 1920, 64);
  make_map(enc, &tmW1, d_in[4], 640, 1536, 32);
  make_map(enc, &tmW2, d_in[6], 1536, 640, 32);
  make_map(enc, &tmWo, d_in[2], 640, 640, 32);
  make_map(enc, &tmH, pH, 2048, 1536, 64);
  make_map(enc, &tmHst, pH, 2048, 1536, 32);
  make_map(enc, &tmO, pO, 2048, 640, 64);
  make_map(enc, &tmOut, d_out, 2048, 640, 80);
  Args a;
  a.x = (const __nv_bfloat16*)d_in[0];
  a.w1 = (const __nv_bfloat16*)d_in[4];
  a.b1 = (const __nv_bfloat16*)d_in[5];
  a.b2 = (const __nv_bfloat16*)d_in[7];
  a.gate_w = (const __nv_bfloat16*)d_in[8];
  a.zero = 0;
  fused_kernel<<<128, 640, SM_BYTES>>>(tmX, tmWqkv, tmW1, tmW2, tmWo, tmH, tmHst, tmO, tmOut, a);
}
```
